```python
import torch

def _softmax(x, axis=-1):
    return torch.softmax(x, dim=axis)
def _gelu(x):
    return torch.nn.functional.gelu(x, approximate="tanh")
def _silu(x):
    return torch.nn.functional.silu(x)
def _sigmoid(x):
    return torch.sigmoid(x)
def _layernorm(x, axis=-1, eps=1e-5):
    m = x.mean(dim=axis, keepdim=True)
    v = x.var(dim=axis, keepdim=True, unbiased=False)
    return (x - m) / torch.sqrt(v + eps)
def _scatter_add(tgt, idx, src, axis=0):
    return tgt.clone().index_add_(axis, idx, src)
def _segment_sum(src, seg, n):
    out = torch.zeros((n,) + src.shape[1:], dtype=src.dtype)
    return out.index_add_(0, seg, src)
def _pad(x, pw):
    flat = tuple(v for pair in reversed(pw) for v in pair)
    return torch.nn.functional.pad(x, flat)

kernel_name = 'standalone__deep_cross_xdeepfm__recsys'

def setup_inputs():

    _w = (lambda a: (lambda t: t.to(torch.bfloat16) if t.is_floating_point() else t)(torch.as_tensor(a)))
    B, F, D, L = 4096, 26, 16, 3
    V = min(1000000, 100000)
    Din = F * D
    return {
        "idx": _w((lambda lo, hi, *s: torch.randint(lo, hi, s))(0, V, B, F).to(torch.int64)),
        "table": _w((lambda *s: torch.randn(*s, dtype=torch.bfloat16) * 0.8)(V, D)),
        "ws_cin": _w((lambda *s: torch.randn(*s, dtype=torch.bfloat16) * 0.2)(L, F, F, F) * (1.0 / F)),
        "w_cin_out": _w((lambda *s: torch.randn(*s, dtype=torch.bfloat16) * 0.2)(L * F) * ((L * F) ** -0.5)),
        "w_dnn1": _w((lambda *s: torch.randn(*s, dtype=torch.bfloat16) * 0.8)(Din, Din) * (Din ** -0.5)),
        "b_dnn1": _w((lambda *s: torch.randn(*s, dtype=torch.bfloat16) * 3.2)(Din) * 0.1),
        "w_dnn2": _w((lambda *s: torch.randn(*s, dtype=torch.bfloat16) * 0.2)(Din) * (Din ** -0.5)),
        "b_out": _w((lambda *s: torch.randn(*s, dtype=torch.bfloat16) * 0.4)(1)),
    }

def reference(idx, table, ws_cin, w_cin_out, w_dnn1, b_dnn1, w_dnn2, b_out):
    x0 = table[idx]
    B = x0.shape[0]
    L = ws_cin.shape[0]
    xk = x0
    pooled = []
    for l in range(L):
        xk = torch.einsum('bid,bjd,hij->bhd', xk, x0, ws_cin[l])
        pooled.append(xk.sum(axis=-1))
    p_plus = torch.stack(pooled, axis=1).reshape(B, -1)
    logit_cin = p_plus @ w_cin_out
    h = x0.reshape(B, -1)
    h = _gelu(h @ w_dnn1 + b_dnn1)
    logit_dnn = h @ w_dnn2
    return logit_cin + logit_dnn + b_out
```

```cpp
#include <cuda_runtime.h>
#include <cuda_bf16.h>
#include <cuda.h>
#include <stdint.h>

#define DEV __device__ __forceinline__

namespace {

constexpr uint32_t kGatherPace = 500;
constexpr uint32_t kW1Start = 1600;
constexpr uint32_t kW1Gap = 600;
constexpr int kW1AfterCin = 5;
constexpr uint32_t kPollStart = 3500;

constexpr int kThreads = 512;
constexpr int kFold = 4;
constexpr int kMain = 128;

constexpr uint32_t WSLOT = 24576;
constexpr uint32_t WS_OFF = 4 * WSLOT;
constexpr uint32_t CW_OFF = WS_OFF + 448 * 32;
constexpr uint32_t CINW_BYTES = 24 * 1792;
constexpr uint32_t X_OFF = CW_OFF + CINW_BYTES;
constexpr uint32_t XF = 1056, XH = 528, XB = 27 * XF;
constexpr uint32_t CINP_OFF = X_OFF + 2 * XB;
constexpr uint32_t BW_OFF = CINP_OFF + 8 * 384;
constexpr uint32_t PART_OFF = BW_OFF + 208 * 8;
constexpr uint32_t IDX_OFF = PART_OFF + 68 * 4;
constexpr uint32_t BAR_OFF = IDX_OFF + 3328;
constexpr uint32_t B_XLOC = BAR_OFF, B_DFULL = BAR_OFF + 56, B_SLOT = BAR_OFF + 112, B_FIN = BAR_OFF + 136, B_CINREQ = BAR_OFF + 144, B_CINW = BAR_OFF + 152;
constexpr uint32_t SMEM_BYTES = BAR_OFF + 192;
constexpr uint32_t CW_BLK = CINW_BYTES / 4;

__device__ uint4 g_cinw[CINW_BYTES / 16];
constexpr int kFlags = 32;
__device__ unsigned int g_sync[(kFlags + 1) * 32];

__device__ __align__(16) const uint32_t g_tab[768] = {
    0x00900004u, 0x11fc0094u, 0x08a8081cu, 0x11fc08acu, 0x0870003cu, 0x087400ccu, 0x0c600058u, 0x0c6400e8u,
    0x01200008u, 0x01240098u, 0x09380820u, 0x093c08b0u, 0x09000040u, 0x090400d0u, 0x0cf0005cu, 0x0cf400ecu,
    0x01b0000cu, 0x01b4009cu, 0x09c80824u, 0x09cc08b4u, 0x09900044u, 0x099400d4u, 0x0d800060u, 0x0d8400f0u,
    0x02400010u, 0x024400a0u, 0x0a580828u, 0x0a5c08b8u, 0x0a200048u, 0x0a2400d8u, 0x0e100064u, 0x0e1400f4u,
    0x02d00014u, 0x02d400a4u, 0x0ae8082cu, 0x0aec08bcu, 0x0ab0004cu, 0x0ab400dcu, 0x11fc0068u, 0x11fc00f8u,
    0x03600018u, 0x036400a8u, 0x0b780830u, 0x0b7c08c0u, 0x0b400050u, 0x0b4400e0u, 0x07500034u, 0x075400c4u,
    0x11fc0000u, 0x03f400acu, 0x11fc0818u, 0x0c0c08c4u, 0x07e00038u, 0x0bd400e4u, 0x0bd00054u, 0x07e400c8u,
    0x01b8012cu, 0x11fc01bcu, 0x09d00944u, 0x11fc09d4u, 0x09980164u, 0x099c01f4u, 0x0d880180u, 0x0d8c0210u,
    0x02480130u, 0x024c01c0u, 0x0a600948u, 0x0a6409d8u, 0x0a280168u, 0x0a2c01f8u, 0x0e180184u, 0x0e1c0214u,
    0x02d80134u, 0x02dc01c4u, 0x0af0094cu, 0x0af409dcu, 0x0ab8016cu, 0x0abc01fcu, 0x11fc0188u, 0x11fc0218u,
    0x03680138u, 0x036c01c8u, 0x0b800950u, 0x0b8409e0u, 0x0b480170u, 0x0b4c0200u, 0x07580154u, 0x075c01e4u,
    0x03f8013cu, 0x03fc01ccu, 0x0c100954u, 0x0c1409e4u, 0x0bd80174u, 0x0bdc0204u, 0x07e80158u, 0x07ec01e8u,
    0x04880140u, 0x048c01d0u, 0x0ca00958u, 0x0ca409e8u, 0x0c680178u, 0x0c6c0208u, 0x0878015cu, 0x087c01ecu,
    0x11fc0128u, 0x051c01d4u, 0x11fc0940u, 0x0d3409ecu, 0x09080160u, 0x0cfc020cu, 0x0cf8017cu, 0x090c01f0u,
    0x02e00254u, 0x11fc02e4u, 0x0af80a6cu, 0x11fc0afcu, 0x0ac0028cu, 0x0ac4031cu, 0x11fc02a8u, 0x11fc0338u,
    0x03700258u, 0x037402e8u, 0x0b880a70u, 0x0b8c0b00u, 0x0b500290u, 0x0b540320u, 0x07600274u, 0x07640304u,
    0x0400025cu, 0x040402ecu, 0x0c180a74u, 0x0c1c0b04u, 0x0be00294u, 0x0be40324u, 0x07f00278u, 0x07f40308u,
    0x04900260u, 0x049402f0u, 0x0ca80a78u, 0x0cac0b08u, 0x0c700298u, 0x0c740328u, 0x0880027cu, 0x0884030cu,
    0x05200264u, 0x052402f4u, 0x0d380a7cu, 0x0d3c0b0cu, 0x0d00029cu, 0x0d04032cu, 0x09100280u, 0x09140310u,
    0x05b00268u, 0x05b402f8u, 0x0dc80a80u, 0x0dcc0b10u, 0x0d9002a0u, 0x0d940330u, 0x09a00284u, 0x09a40314u,
    0x11fc0250u, 0x064402fcu, 0x11fc0a68u, 0x0e5c0b14u, 0x0a300288u, 0x0e240334u, 0x0e2002a4u, 0x0a340318u,
    0x0408037cu, 0x11fc040cu, 0x0c200b94u, 0x11fc0c24u, 0x0be803b4u, 0x0bec0444u, 0x07f80398u, 0x07fc0428u,
    0x04980380u, 0x049c0410u, 0x0cb00b98u, 0x0cb40c28u, 0x0c7803b8u, 0x0c7c0448u, 0x0888039cu, 0x088c042cu,
    0x05280384u, 0x052c0414u, 0x0d400b9cu, 0x0d440c2cu, 0x0d0803bcu, 0x0d0c044cu, 0x091803a0u, 0x091c0430u,
    0x05b80388u, 0x05bc0418u, 0x0dd00ba0u, 0x0dd40c30u, 0x0d9803c0u, 0x0d9c0450u, 0x09a803a4u, 0x09ac0434u,
    0x0648038cu, 0x064c041cu, 0x0e600ba4u, 0x0e640c34u, 0x0e2803c4u, 0x0e2c0454u, 0x0a3803a8u, 0x0a3c0438u,
    0x06d80390u, 0x06dc0420u, 0x0b7407a0u, 0x0c0407a4u, 0x11fc03c8u, 0x11fc0458u, 0x0ac803acu, 0x0acc043cu,
    0x11fc0378u, 0x03f0001cu, 0x11fc0b90u, 0x0c080834u, 0x0b5803b0u, 0x076c0424u, 0x07680394u, 0x0b5c0440u,
    0x053004a4u, 0x11fc0534u, 0x0d480cbcu, 0x11fc0d4cu, 0x0d1004dcu, 0x0d14056cu, 0x092004c0u, 0x09240550u,
    0x05c004a8u, 0x05c40538u, 0x0dd80cc0u, 0x0ddc0d50u, 0x0da004e0u, 0x0da40570u, 0x09b004c4u, 0x09b40554u,
    0x065004acu, 0x0654053cu, 0x0e680cc4u, 0x0e6c0d54u, 0x0e3004e4u, 0x0e340574u, 0x0a4004c8u, 0x0a440558u,
    0x06e004b0u, 0x06e40540u, 0x0c9407a8u, 0x0d2407acu, 0x11fc04e8u, 0x11fc0578u, 0x0ad004ccu, 0x0ad4055cu,
    0x04800020u, 0x05100024u, 0x0c980838u, 0x0d28083cu, 0x077004b4u, 0x07740544u, 0x0b6004d0u, 0x0b640560u,
    0x048400b0u, 0x051400b4u, 0x0c9c08c8u, 0x0d2c08ccu, 0x080004b8u, 0x08040548u, 0x0bf004d4u, 0x0bf40564u,
    0x11fc04a0u, 0x05180144u, 0x11fc0cb8u, 0x0d30095cu, 0x0c8004d8u, 0x0894054cu, 0x089004bcu, 0x0c840568u,
    0x065805ccu, 0x11fc065cu, 0x0e700de4u, 0x11fc0e74u, 0x0e380604u, 0x0e3c0694u, 0x0a4805e8u, 0x0a4c0678u,
    0x06e805d0u, 0x06ec0660u, 0x0db407b0u, 0x0e4407b4u, 0x11fc0608u, 0x11fc0698u, 0x0ad805ecu, 0x0adc067cu,
    0x05a00028u, 0x0630002cu, 0x0db80840u, 0x0e480844u, 0x077805d4u, 0x077c0664u, 0x0b6805f0u, 0x0b6c0680u,
    0x05a400b8u, 0x063400bcu, 0x0dbc08d0u, 0x0e4c08d4u, 0x080805d8u, 0x080c0668u, 0x0bf805f4u, 0x0bfc0684u,
    0x05a80148u, 0x0638014cu, 0x0dc00960u, 0x0e500964u, 0x089805dcu, 0x089c066cu, 0x0c8805f8u, 0x0c8c0688u,
    0x05ac01d8u, 0x063c01dcu, 0x0dc409f0u, 0x0e5409f4u, 0x092805e0u, 0x092c0670u, 0x0d1805fcu, 0x0d1c068cu,
    0x11fc05c8u, 0x0640026cu, 0x11fc0de0u, 0x0e580a84u, 0x0da80600u, 0x09bc0674u, 0x09b805e4u, 0x0dac0690u,
    0x11fc06f0u, 0x06c00030u, 0x11fc0784u, 0x08140788u, 0x11fc0728u, 0x078006f4u, 0x0ae0070cu, 0x0b700710u,
    0x06c400c0u, 0x06c80150u, 0x08a4078cu, 0x09340790u, 0x081006f8u, 0x08a006fcu, 0x0c000714u, 0x0c900718u,
    0x06cc01e0u, 0x06d00270u, 0x09c40794u, 0x0a540798u, 0x09300700u, 0x09c00704u, 0x0d20071cu, 0x0db00720u,
    0x06d40300u, 0x11fc07b8u, 0x0ae4079cu, 0x11fc0968u, 0x0a500708u, 0x11fc0b18u, 0x0e400724u, 0x11fc0cc8u,
    0x11fc0848u, 0x11fc08d8u, 0x11fc09f8u, 0x11fc0a88u, 0x11fc0ba8u, 0x11fc0c38u, 0x11fc0d58u, 0x11fc0de8u,
    0x11fc11fcu, 0x11fc11fcu, 0x11fc11fcu, 0x11fc11fcu, 0x11fc11fcu, 0x11fc11fcu, 0x11fc0e78u, 0x11fc116cu,
    0x001a0001u, 0x02a4001bu, 0x0194017bu, 0x02a40195u, 0x0186000fu, 0x01870029u, 0x023c0016u, 0x023d0030u,
    0x00340002u, 0x0035001cu, 0x01ae017cu, 0x01af0196u, 0x01a00010u, 0x01a1002au, 0x02560017u, 0x02570031u,
    0x004e0003u, 0x004f001du, 0x01c8017du, 0x01c90197u, 0x01ba0011u, 0x01bb002bu, 0x02700018u, 0x02710032u,
    0x00680004u, 0x0069001eu, 0x01e2017eu, 0x01e30198u, 0x01d40012u, 0x01d5002cu, 0x028a0019u, 0x028b0033u,
    0x00820005u, 0x0083001fu, 0x01fc017fu, 0x01fd0199u, 0x01ee0013u, 0x01ef002du, 0x02a402a4u, 0x02a402a4u,
    0x009c0006u, 0x009d0020u, 0x02160180u, 0x0217019au, 0x02080014u, 0x0209002eu, 0x0152000du, 0x01530027u,
    0x02a40000u, 0x00b70021u, 0x02a4017au, 0x0231019bu, 0x016c000eu, 0x0223002fu, 0x02220015u, 0x016d0028u,
    0x00500037u, 0x02a40051u, 0x01ca01b1u, 0x02a401cbu, 0x01bc0045u, 0x01bd005fu, 0x0272004cu, 0x02730066u,
    0x006a0038u, 0x006b0052u, 0x01e401b2u, 0x01e501ccu, 0x01d60046u, 0x01d70060u, 0x028c004du, 0x028d0067u,
    0x00840039u, 0x00850053u, 0x01fe01b3u, 0x01ff01cdu, 0x01f00047u, 0x01f10061u, 0x02a402a4u, 0x02a402a4u,
    0x009e003au, 0x009f0054u, 0x021801b4u, 0x021901ceu, 0x020a0048u, 0x020b0062u, 0x01540041u, 0x0155005bu,
    0x00b8003bu, 0x00b90055u, 0x023201b5u, 0x023301cfu, 0x02240049u, 0x02250063u, 0x016e0042u, 0x016f005cu,
    0x00d2003cu, 0x00d30056u, 0x024c01b6u, 0x024d01d0u, 0x023e004au, 0x023f0064u, 0x01880043u, 0x0189005du,
    0x02a40036u, 0x00ed0057u, 0x02a401b0u, 0x026701d1u, 0x01a20044u, 0x02590065u, 0x0258004bu, 0x01a3005eu,
    0x0086006du, 0x02a40087u, 0x020001e7u, 0x02a40201u, 0x01f2007bu, 0x01f30095u, 0x02a402a4u, 0x02a402a4u,
    0x00a0006eu, 0x00a10088u, 0x021a01e8u, 0x021b0202u, 0x020c007cu, 0x020d0096u, 0x01560075u, 0x0157008fu,
    0x00ba006fu, 0x00bb0089u, 0x023401e9u, 0x02350203u, 0x0226007du, 0x02270097u, 0x01700076u, 0x01710090u,
    0x00d40070u, 0x00d5008au, 0x024e01eau, 0x024f0204u, 0x0240007eu, 0x02410098u, 0x018a0077u, 0x018b0091u,
    0x00ee0071u, 0x00ef008bu, 0x026801ebu, 0x02690205u, 0x025a007fu, 0x025b0099u, 0x01a40078u, 0x01a50092u,
    0x01080072u, 0x0109008cu, 0x028201ecu, 0x02830206u, 0x02740080u, 0x0275009au, 0x01be0079u, 0x01bf0093u,
    0x02a4006cu, 0x0123008du, 0x02a401e6u, 0x029d0207u, 0x01d8007au, 0x028f009bu, 0x028e0081u, 0x01d90094u,
    0x00bc00a3u, 0x02a400bdu, 0x0236021du, 0x02a40237u, 0x022800b1u, 0x022900cbu, 0x017200aau, 0x017300c4u,
    0x00d600a4u, 0x00d700beu, 0x0250021eu, 0x02510238u, 0x024200b2u, 0x024300ccu, 0x018c00abu, 0x018d00c5u,
    0x00f000a5u, 0x00f100bfu, 0x026a021fu, 0x026b0239u, 0x025c00b3u, 0x025d00cdu, 0x01a600acu, 0x01a700c6u,
    0x010a00a6u, 0x010b00c0u, 0x02840220u, 0x0285023au, 0x027600b4u, 0x027700ceu, 0x01c000adu, 0x01c100c7u,
    0x012400a7u, 0x012500c1u, 0x029e0221u, 0x029f023bu, 0x029000b5u, 0x029100cfu, 0x01da00aeu, 0x01db00c8u,
    0x013e00a8u, 0x013f00c2u, 0x02150166u, 0x022f0167u, 0x02a402a4u, 0x02a402a4u, 0x01f400afu, 0x01f500c9u,
    0x02a400a2u, 0x00b60007u, 0x02a4021cu, 0x02300181u, 0x020e00b0u, 0x015900c3u, 0x015800a9u, 0x020f00cau,
    0x00f200d9u, 0x02a400f3u, 0x026c0253u, 0x02a4026du, 0x025e00e7u, 0x025f0101u, 0x01a800e0u, 0x01a900fau,
    0x010c00dau, 0x010d00f4u, 0x02860254u, 0x0287026eu, 0x027800e8u, 0x02790102u, 0x01c200e1u, 0x01c300fbu,
    0x012600dbu, 0x012700f5u, 0x02a00255u, 0x02a1026fu, 0x029200e9u, 0x02930103u, 0x01dc00e2u, 0x01dd00fcu,
    0x014000dcu, 0x014100f6u, 0x02490168u, 0x02630169u, 0x02a402a4u, 0x02a402a4u, 0x01f600e3u, 0x01f700fdu,
    0x00d00008u, 0x00ea0009u, 0x024a0182u, 0x02640183u, 0x015a00ddu, 0x015b00f7u, 0x021000e4u, 0x021100feu,
    0x00d10022u, 0x00eb0023u, 0x024b019cu, 0x0265019du, 0x017400deu, 0x017500f8u, 0x022a00e5u, 0x022b00ffu,
    0x02a400d8u, 0x00ec003du, 0x02a40252u, 0x026601b7u, 0x024400e6u, 0x018f00f9u, 0x018e00dfu, 0x02450100u,
    0x0128010fu, 0x02a40129u, 0x02a20289u, 0x02a402a3u, 0x0294011du, 0x02950137u, 0x01de0116u, 0x01df0130u,
    0x01420110u, 0x0143012au, 0x027d016au, 0x0297016bu, 0x02a402a4u, 0x02a402a4u, 0x01f80117u, 0x01f90131u,
    0x0104000au, 0x011e000bu, 0x027e0184u, 0x02980185u, 0x015c0111u, 0x015d012bu, 0x02120118u, 0x02130132u,
    0x01050024u, 0x011f0025u, 0x027f019eu, 0x0299019fu, 0x01760112u, 0x0177012cu, 0x022c0119u, 0x022d0133u,
    0x0106003eu, 0x0120003fu, 0x028001b8u, 0x029a01b9u, 0x01900113u, 0x0191012du, 0x0246011au, 0x02470134u,
    0x01070058u, 0x01210059u, 0x028101d2u, 0x029b01d3u, 0x01aa0114u, 0x01ab012eu, 0x0260011bu, 0x02610135u,
    0x02a4010eu, 0x01220073u, 0x02a40288u, 0x029c01edu, 0x027a011cu, 0x01c5012fu, 0x01c40115u, 0x027b0136u,
    0x02a40144u, 0x0138000cu, 0x02a4015fu, 0x01790160u, 0x02a402a4u, 0x015e0145u, 0x01fa014bu, 0x0214014cu,
    0x01390026u, 0x013a0040u, 0x01930161u, 0x01ad0162u, 0x01780146u, 0x01920147u, 0x022e014du, 0x0248014eu,
    0x013b005au, 0x013c0074u, 0x01c70163u, 0x01e10164u, 0x01ac0148u, 0x01c60149u, 0x0262014fu, 0x027c0150u,
    0x013d008eu, 0x02a402a4u, 0x01fb0165u, 0x02a402a4u, 0x01e0014au, 0x02a402a4u, 0x02960151u, 0x02a402a4u,
    0x02a402a4u, 0x02a402a4u, 0x02a402a4u, 0x02a402a4u, 0x02a402a4u, 0x02a402a4u, 0x02a402a4u, 0x02a402a4u,
    0x02a402a4u, 0x02a402a4u, 0x02a402a4u, 0x02a402a4u, 0x02a402a4u, 0x02a402a4u, 0x02a402a4u, 0x02a402a4u,
};

DEV uint32_t smem_u32(const void* p) { return (uint32_t)__cvta_generic_to_shared(p); }
DEV void mbar_init(uint32_t bar, uint32_t cnt) { asm volatile("mbarrier.init.shared::cta.b64 [%0], %1;" :: "r"(bar), "r"(cnt) : "memory"); }
DEV void mbar_expect_tx(uint32_t bar, uint32_t bytes) { asm volatile("mbarrier.arrive.expect_tx.shared::cta.b64 _, [%0], %1;" :: "r"(bar), "r"(bytes) : "memory"); }
DEV void mbar_arrive(uint32_t bar) { asm volatile("mbarrier.arrive.shared::cta.b64 _, [%0];" :: "r"(bar) : "memory"); }
DEV void mbar_wait(uint32_t bar) {
    uint32_t ok;
#pragma unroll 1
    for (uint32_t it = 0; it < (1u << 22); it++) {
        asm volatile("{\n.reg .pred p;\nmbarrier.try_wait.parity.shared::cta.b64 p, [%1], 0;\nselp.u32 %0, 1, 0, p;\n}" : "=r"(ok) : "r"(bar) : "memory");
        if (ok) return;
    }
    __trap();
}
DEV void fence_async_smem() { asm volatile("fence.proxy.async.shared::cta;" ::: "memory"); }
DEV void wg_fence() { asm volatile("wgmma.fence.sync.aligned;" ::: "memory"); }
DEV void wg_commit() { asm volatile("wgmma.commit_group.sync.aligned;" ::: "memory"); }
template <int N> DEV void wg_wait() { asm volatile("wgmma.wait_group.sync.aligned %0;" :: "n"(N) : "memory"); }
DEV uint64_t mkdesc(uint32_t addr, uint32_t lbo, uint32_t sbo, uint32_t sw) {
    return (uint64_t)((addr & 0x3FFFF) >> 4) | ((uint64_t)(lbo >> 4) << 16) | ((uint64_t)(sbo >> 4) << 32) | ((uint64_t)sw << 62);
}
DEV uint32_t lds32(uint32_t a) { uint32_t v; asm volatile("ld.shared.b32 %0, [%1];" : "=r"(v) : "r"(a)); return v; }
DEV float4 lds128f(uint32_t a) { float4 v; asm volatile("ld.shared.v4.f32 {%0,%1,%2,%3}, [%4];" : "=f"(v.x), "=f"(v.y), "=f"(v.z), "=f"(v.w) : "r"(a)); return v; }
DEV void sts32f(uint32_t a, float v) { asm volatile("st.shared.f32 [%0], %1;" :: "r"(a), "f"(v) : "memory"); }
DEV float lds32f(uint32_t a) { float v; asm volatile("ld.shared.f32 %0, [%1];" : "=f"(v) : "r"(a) : "memory"); return v; }
DEV uint32_t mapa(uint32_t a, uint32_t rank) { uint32_t r; asm volatile("mapa.shared::cluster.u32 %0, %1, %2;" : "=r"(r) : "r"(a), "r"(rank)); return r; }
DEV uint32_t prmt(uint32_t a, uint32_t b, uint32_t s) { uint32_t r; asm("prmt.b32 %0, %1, %2, %3;" : "=r"(r) : "r"(a), "r"(b), "r"(s)); return r; }
DEV uint32_t bmul(uint32_t a, uint32_t b) { uint32_t r; asm("mul.rn.bf16x2 %0, %1, %2;" : "=r"(r) : "r"(a), "r"(b)); return r; }
DEV uint32_t bmul_lo(uint32_t a, uint32_t b) { uint32_t r; asm("{\n.reg .b16 l, h;\n.reg .b32 t;\nmov.b32 {l, h}, %2;\nmov.b32 t, {l, l};\nmul.rn.bf16x2 %0, %1, t;\n}" : "=r"(r) : "r"(a), "r"(b)); return r; }
DEV uint32_t bmul_hi(uint32_t a, uint32_t b) { uint32_t r; asm("{\n.reg .b16 l, h;\n.reg .b32 t;\nmov.b32 {l, h}, %2;\nmov.b32 t, {h, h};\nmul.rn.bf16x2 %0, %1, t;\n}" : "=r"(r) : "r"(a), "r"(b)); return r; }
DEV float bf_lo(uint32_t v) { return __uint_as_float(v << 16); }
DEV float bf_hi(uint32_t v) { return __uint_as_float(v & 0xffff0000u); }
DEV float bf2f(const __nv_bfloat16* p) { return __uint_as_float((uint32_t)(*(const uint16_t*)p) << 16); }
DEV uint32_t pack_bf16(float lo, float hi) { uint32_t r; asm("cvt.rn.bf16x2.f32 %0, %1, %2;" : "=r"(r) : "f"(hi), "f"(lo)); return r; }
DEV float tanh_fast(float x) { float y; asm("tanh.approx.f32 %0, %1;" : "=f"(y) : "f"(x)); return y; }

DEV void tma3(uint32_t dst, const CUtensorMap* m, int x, int y, int z, uint32_t bar) {
    asm volatile("cp.async.bulk.tensor.3d.shared::cluster.global.mbarrier::complete_tx::bytes [%0], [%1, {%3, %4, %5}], [%2];"
                 :: "r"(dst), "l"(m), "r"(bar), "r"(x), "r"(y), "r"(z) : "memory");
}

DEV void wgmma_rs_n192(float (&d)[96], const uint32_t (&a)[4], uint64_t db, int sd) {
    asm volatile("{\n.reg .pred p;\nsetp.ne.b32 p, %101, 0;\n"
        "wgmma.mma_async.sync.aligned.m64n192k16.f32.bf16.bf16 "
        "{%0, %1, %2, %3, %4, %5, %6, %7, %8, %9, %10, %11, %12, %13, %14, %15, %16, %17, %18, %19, %20, %21, %22, %23, %24, %25, %26, %27, %28, %29, %30, %31, %32, %33, %34, %35, %36, %37, %38, %39, %40, %41, %42, %43, %44, %45, %46, %47, %48, %49, %50, %51, %52, %53, %54, %55, %56, %57, %58, %59, %60, %61, %62, %63, %64, %65, %66, %67, %68, %69, %70, %71, %72, %73, %74, %75, %76, %77, %78, %79, %80, %81, %82, %83, %84, %85, %86, %87, %88, %89, %90, %91, %92, %93, %94, %95}, "
        "{%96, %97, %98, %99}, %100, p, 1, 1, 1;\n}\n"
        : "+f"(d[0]), "+f"(d[1]), "+f"(d[2]), "+f"(d[3]), "+f"(d[4]), "+f"(d[5]), "+f"(d[6]), "+f"(d[7]), "+f"(d[8]), "+f"(d[9]), "+f"(d[10]), "+f"(d[11]), "+f"(d[12]), "+f"(d[13]), "+f"(d[14]), "+f"(d[15]), "+f"(d[16]), "+f"(d[17]), "+f"(d[18]), "+f"(d[19]), "+f"(d[20]), "+f"(d[21]), "+f"(d[22]), "+f"(d[23]), "+f"(d[24]), "+f"(d[25]), "+f"(d[26]), "+f"(d[27]), "+f"(d[28]), "+f"(d[29]), "+f"(d[30]), "+f"(d[31]), "+f"(d[32]), "+f"(d[33]), "+f"(d[34]), "+f"(d[35]), "+f"(d[36]), "+f"(d[37]), "+f"(d[38]), "+f"(d[39]), "+f"(d[40]), "+f"(d[41]), "+f"(d[42]), "+f"(d[43]), "+f"(d[44]), "+f"(d[45]), "+f"(d[46]), "+f"(d[47]), "+f"(d[48]), "+f"(d[49]), "+f"(d[50]), "+f"(d[51]), "+f"(d[52]), "+f"(d[53]), "+f"(d[54]), "+f"(d[55]), "+f"(d[56]), "+f"(d[57]), "+f"(d[58]), "+f"(d[59]), "+f"(d[60]), "+f"(d[61]), "+f"(d[62]), "+f"(d[63]), "+f"(d[64]), "+f"(d[65]), "+f"(d[66]), "+f"(d[67]), "+f"(d[68]), "+f"(d[69]), "+f"(d[70]), "+f"(d[71]), "+f"(d[72]), "+f"(d[73]), "+f"(d[74]), "+f"(d[75]), "+f"(d[76]), "+f"(d[77]), "+f"(d[78]), "+f"(d[79]), "+f"(d[80]), "+f"(d[81]), "+f"(d[82]), "+f"(d[83]), "+f"(d[84]), "+f"(d[85]), "+f"(d[86]), "+f"(d[87]), "+f"(d[88]), "+f"(d[89]), "+f"(d[90]), "+f"(d[91]), "+f"(d[92]), "+f"(d[93]), "+f"(d[94]), "+f"(d[95])
        : "r"(a[0]), "r"(a[1]), "r"(a[2]), "r"(a[3]), "l"(db), "r"(sd));
}
DEV void wgmma_rs_n16(float (&d)[8], const uint32_t (&a)[4], uint64_t db, int sd) {
    asm volatile("{\n.reg .pred p;\nsetp.ne.b32 p, %13, 0;\n"
        "wgmma.mma_async.sync.aligned.m64n16k16.f32.bf16.bf16 {%0, %1, %2, %3, %4, %5, %6, %7}, {%8, %9, %10, %11}, %12, p, 1, 1, 1;\n}\n"
        : "+f"(d[0]), "+f"(d[1]), "+f"(d[2]), "+f"(d[3]), "+f"(d[4]), "+f"(d[5]), "+f"(d[6]), "+f"(d[7])
        : "r"(a[0]), "r"(a[1]), "r"(a[2]), "r"(a[3]), "l"(db), "r"(sd));
}
DEV void wgmma_rs_n56(float (&d)[28], uint32_t a0, uint32_t a1, uint32_t a2, uint32_t a3, uint64_t db, int sd) {
    asm volatile("{\n.reg .pred p;\nsetp.ne.b32 p, %33, 0;\n"
        "wgmma.mma_async.sync.aligned.m64n56k16.f32.bf16.bf16 "
        "{%0, %1, %2, %3, %4, %5, %6, %7, %8, %9, %10, %11, %12, %13, %14, %15, %16, %17, %18, %19, %20, %21, %22, %23, %24, %25, %26, %27}, "
        "{%28, %29, %30, %31}, %32, p, 1, 1, 0;\n}\n"
        : "+f"(d[0]), "+f"(d[1]), "+f"(d[2]), "+f"(d[3]), "+f"(d[4]), "+f"(d[5]), "+f"(d[6]), "+f"(d[7]), "+f"(d[8]), "+f"(d[9]), "+f"(d[10]), "+f"(d[11]),
          "+f"(d[12]), "+f"(d[13]), "+f"(d[14]), "+f"(d[15]), "+f"(d[16]), "+f"(d[17]), "+f"(d[18]), "+f"(d[19]), "+f"(d[20]), "+f"(d[21]), "+f"(d[22]), "+f"(d[23]),
          "+f"(d[24]), "+f"(d[25]), "+f"(d[26]), "+f"(d[27])
        : "r"(a0), "r"(a1), "r"(a2), "r"(a3), "l"(db), "r"(sd));
}

DEV void gelu_dot(float x, float hw, float& s) {
    const float k0 = 0.7978845608028654f, k1 = 0.7978845608028654f * 0.044715f;
    float u = x * fmaf(x * x, k1, k0);
    s = fmaf(fmaf(x, tanh_fast(u), x), hw, s);
}

template <int KP>
DEV void kpair(const uint32_t (&L)[13], const uint32_t (&R)[19], const uint32_t (&E)[5], uint32_t& lo, uint32_t& hi) {
    if constexpr (KP < 42) {
        constexpr int m = 2 * (KP / 7), r = KP % 7;
        const uint32_t l0 = prmt(L[m], L[m + 1], 0x5410), l1 = prmt(L[m], L[m + 1], 0x7632);
        if constexpr (r < 6) { lo = bmul_lo(l0, R[m + 1 + r]); hi = bmul_hi(l1, R[m + 1 + r]); }
        else { lo = bmul(l0, prmt(R[m], R[m + 7], 0x5410)); hi = bmul(l1, prmt(R[m], R[m + 7], 0x7632)); }
    } else if constexpr (KP < 45) {
        constexpr int n = 12 + 2 * (KP - 42);
        lo = bmul_lo(prmt(R[n], R[n + 1], 0x5410), L[12]); hi = bmul_hi(prmt(R[n], R[n + 1], 0x7632), L[12]);
    } else if constexpr (KP == 45) {
        const uint32_t p = bmul(L[12], R[18]);
        lo = prmt(p, E[0], 0x5410); hi = prmt(p, E[0], 0x7632);
    } else {
        constexpr int e = 1 + 2 * (KP - 46);
        lo = prmt(E[e], E[e + 1], 0x5410); hi = prmt(E[e], E[e + 1], 0x7632);
    }
}
struct XAddr { uint32_t LA, LB, RA, RB, RC, RD, E; };
struct XReg { uint32_t L[13], R[19], E[5]; };
template <int m> DEV void ldL(XReg& x, const XAddr& a, uint32_t o) { x.L[m] = lds32((m < 12 ? a.LA : a.LB) + m * XF + o); }
template <int n> DEV void ldR(XReg& x, const XAddr& a, uint32_t o) { x.R[n] = lds32((n < 6 ? a.RA : n < 12 ? a.RB : n == 12 ? a.RC : a.RD) + n * XF + o); }
template <int e> DEV void ldE(XReg& x, const XAddr& a, uint32_t o) { x.E[e] = lds32(a.E + e * XF + o); }
template <int g> DEV void cin_loads(XReg& x, const XAddr& a, uint32_t o) {
    if constexpr (g == 0) { ldL<0>(x, a, o); ldL<1>(x, a, o); ldR<1>(x, a, o); ldR<2>(x, a, o); ldR<3>(x, a, o); ldR<4>(x, a, o); ldR<5>(x, a, o); ldR<6>(x, a, o); }
    else if constexpr (g == 1) { ldR<0>(x, a, o); ldR<7>(x, a, o); ldL<2>(x, a, o); ldL<3>(x, a, o); }
    else if constexpr (g <= 5) { ldR<2 * g + 4>(x, a, o); ldR<2 * g + 5>(x, a, o); ldL<2 * g>(x, a, o); ldL<2 * g + 1>(x, a, o); }
    else if constexpr (g == 6) { ldR<16>(x, a, o); ldR<17>(x, a, o); }
    else { ldL<12>(x, a, o); ldR<18>(x, a, o); ldE<0>(x, a, o); ldE<1>(x, a, o); ldE<2>(x, a, o); ldE<3>(x, a, o); ldE<4>(x, a, o); }
}
template <int GR> DEV void cin_group(float (&d)[28], const XReg& x, uint64_t db) {
    uint32_t a[12];
    kpair<6 * GR + 0>(x.L, x.R, x.E, a[0], a[1]);
    kpair<6 * GR + 1>(x.L, x.R, x.E, a[2], a[3]);
    kpair<6 * GR + 2>(x.L, x.R, x.E, a[4], a[5]);
    kpair<6 * GR + 3>(x.L, x.R, x.E, a[6], a[7]);
    kpair<6 * GR + 4>(x.L, x.R, x.E, a[8], a[9]);
    kpair<6 * GR + 5>(x.L, x.R, x.E, a[10], a[11]);
    wg_fence();
#pragma unroll
    for (int k = 0; k < 3; k++)
        wgmma_rs_n56(d, a[4 * k], a[4 * k + 1], a[4 * k + 2], a[4 * k + 3], db + (uint64_t)((((3 * GR + k) / 6) * CW_BLK + ((3 * GR + k) % 6) * 256) >> 4), (3 * GR + k) != 0);
    wg_commit();
}
DEV float cin_dot(float (&d)[28]) {
#pragma unroll
    for (int i = 0; i < 28; i++) asm volatile("" : "+f"(d[i]) :: "memory");
    float s0 = d[0] * d[1], s1 = d[2] * d[3];
#pragma unroll
    for (int g = 1; g < 7; g++) { s0 = fmaf(d[4 * g], d[4 * g + 1], s0); s1 = fmaf(d[4 * g + 2], d[4 * g + 3], s1); }
    s0 += s1;
    asm volatile("" : "+f"(s0) :: "memory");
    return s0;
}
template <bool PREV, bool NEXT>
DEV void cin_tile(float (&d)[28], float (&dp)[28], XReg& x, XReg& xn, const XAddr& a, uint32_t o, uint64_t db, uint32_t pp, uint32_t wb) {
    cin_loads<2>(x, a, o); cin_group<0>(d, x, db);
    cin_loads<3>(x, a, o); cin_group<1>(d, x, db); wg_wait<1>();
    cin_loads<4>(x, a, o);
    if (PREV) sts32f(pp, cin_dot(dp)); else mbar_wait(wb + 8);
    cin_group<2>(d, x, db); wg_wait<1>();
    cin_loads<5>(x, a, o); cin_group<3>(d, x, db); wg_wait<1>();
    cin_loads<6>(x, a, o);
    if (!PREV) mbar_wait(wb + 16);
    cin_group<4>(d, x, db); wg_wait<1>();
    cin_loads<7>(x, a, o); cin_group<5>(d, x, db); wg_wait<1>();
    if (NEXT) cin_loads<0>(xn, a, o + 64);
    if (!PREV) mbar_wait(wb + 24);
    cin_group<6>(d, x, db); wg_wait<1>();
    if (NEXT) cin_loads<1>(xn, a, o + 64);
    cin_group<7>(d, x, db); wg_wait<1>();
}

DEV void wgmma_tf32_n32(float (&d)[16], uint32_t a0, uint32_t a1, uint32_t a2, uint32_t a3, uint64_t db, int sd) {
    asm volatile("{\n.reg .pred p;\nsetp.ne.b32 p, %21, 0;\n"
        "wgmma.mma_async.sync.aligned.m64n32k8.f32.tf32.tf32 {%0, %1, %2, %3, %4, %5, %6, %7, %8, %9, %10, %11, %12, %13, %14, %15}, "
        "{%16, %17, %18, %19}, %20, p, 1, 1;\n}\n"
        : "+f"(d[0]), "+f"(d[1]), "+f"(d[2]), "+f"(d[3]), "+f"(d[4]), "+f"(d[5]), "+f"(d[6]), "+f"(d[7]),
          "+f"(d[8]), "+f"(d[9]), "+f"(d[10]), "+f"(d[11]), "+f"(d[12]), "+f"(d[13]), "+f"(d[14]), "+f"(d[15])
        : "r"(a0), "r"(a1), "r"(a2), "r"(a3), "l"(db), "r"(sd));
}
struct FoldSmem {
    static constexpr uint32_t LB = 35152;
    static constexpr int P = 36, FS = 32 * P + 4;
    static constexpr uint32_t W3 = 0;
    static constexpr uint32_t W2 = LB;
    static constexpr uint32_t W1 = W2 + 26 * 448;
    static constexpr uint32_t M = W1 + 10816;
    static constexpr uint32_t A = M + 4096;
    static constexpr uint32_t IMG = A + 8 * FS * 4;
    static constexpr uint32_t TAB = IMG + 12288;
    static constexpr uint32_t BAR = TAB + 3072;
};
DEV void fold_issue(uint32_t sb, int tid, const uint8_t* __restrict__ src, const uint4* __restrict__ tab) {
    constexpr uint32_t LB = FoldSmem::LB;
    const uint32_t bar = sb + FoldSmem::BAR, f = blockIdx.x;
    if (tid == 0) {
        mbar_init(bar + 8, 1); mbar_init(bar + 32, 160); mbar_init(bar + 40, 1);
        fence_async_smem();
        const uint32_t o1 = f * 10816, n1 = min(LB, o1 + 10816) - o1;
#define BULK(dst, ptr, n, b) asm volatile("cp.async.bulk.shared::cluster.global.mbarrier::complete_tx::bytes [%0], [%1], %2, [%3];" :: "r"(dst), "l"(ptr), "r"(n), "r"(b) : "memory")
        mbar_expect_tx(bar + 8, LB);
        BULK(sb, src + 2 * LB, 11712, bar + 8);
        BULK(sb + 11712, src + 2 * LB + 11712, 11712, bar + 8);
        BULK(sb + 23424, src + 2 * LB + 23424, 11728, bar + 8);
        mbar_expect_tx(bar + 40, n1 + 3072);
        BULK(sb + FoldSmem::TAB, tab, 3072, bar + 40);
        BULK(sb + FoldSmem::W1, src + o1, n1, bar + 40);
#undef BULK
    }
    if (tid >= 352) {
        const uint32_t c = (tid - 352) % 32, h0 = (tid - 352) / 32;
        if (c < 27) {
#pragma unroll
            for (uint32_t i = 0; i < 6; i++) {
                const uint32_t h = h0 + 5 * i, go = (h * 1352 + f * 416) & ~15u;
                if (h < 26 && go + c * 16 < LB)
                    asm volatile("cp.async.cg.shared.global [%0], [%1], 16;" :: "r"(sb + FoldSmem::W2 + h * 448 + c * 16), "l"(src + LB + go + c * 16) : "memory");
            }
        }
    }
}
DEV void fold_role(uint8_t* smem, const __nv_bfloat16* __restrict__ w_out, uint8_t* __restrict__ cinw, unsigned int* sync) {
    constexpr int P = FoldSmem::P, FS = FoldSmem::FS;
    const uint32_t* W3s = (const uint32_t*)(smem + FoldSmem::W3);
    uint8_t* W2s = smem + FoldSmem::W2;
    const uint16_t* W1s = (const uint16_t*)(smem + FoldSmem::W1);
    float* Ms = (float*)(smem + FoldSmem::M);
    float* As = (float*)(smem + FoldSmem::A);
    uint8_t* img = smem + FoldSmem::IMG;
    const uint4* tabs = (const uint4*)(smem + FoldSmem::TAB);
    const uint32_t bar = smem_u32(smem) + FoldSmem::BAR;
    const int tid = threadIdx.x, lane = tid & 31;
    const int warp = __shfl_sync(0xffffffffu, tid >> 5, 0);
    const int f = blockIdx.x;
    const int g = lane >> 2, t = lane & 3;
    if (warp >= 11) {
        asm volatile("bar.sync 3, 192;" ::: "memory");
        asm volatile("cp.async.mbarrier.arrive.noinc.shared::cta.b64 [%0];" :: "r"(bar + 32) : "memory");
    } else if (warp == 0) {
        asm volatile("bar.sync 3, 192;" ::: "memory");
    }
    const int r = lane & 7, oct = min(warp, 11) * 4 + (lane >> 3);
    const bool live = 8 * f + r < 26;
    uint32_t w3w[13];
#pragma unroll
    for (int q = 0; q < 13; q++) w3w[q] = __ldg((const uint32_t*)w_out + 26 + q);
    const uint16_t wc2r = *(const uint16_t*)(w_out + 26 + (tid < 26 ? tid : 0));
    const uint16_t wc1r = *(const uint16_t*)(w_out + min(8 * f + ((tid >> 1) & 7), 25));
    uint8_t* const out16 = img + (oct / 12) * 3072 + (r >> 2) * 1536 + (oct % 12) * 128 + (r & 3) * 32;
    if (warp < 11) asm volatile("bar.sync 4, 352;" ::: "memory");
    if (warp < 11) {
#pragma unroll
        for (int i = 0; i < 3; i++) {
            const int e = tid + i * 352, h = (e >> 7) * 4 + (e & 3), k = ((e >> 5) & 3) * 8 + ((e >> 2) & 7);
            if (e < 1024 && (h >= 26 || k >= 27)) Ms[e] = 0.f;
        }
        if (tid < 16) As[(tid >> 1) * FS + ((tid & 1) ? 31 : 30) * P + 35] = (tid & 1) || 8 * f + (tid >> 1) >= 26 ? 0.f : __uint_as_float((uint32_t)wc1r << 16);
    }
    uint32_t pa[2][4][4];
    if (warp < 11) {
        const int p = min(tid, 337);
        uint32_t w2a = smem_u32(W2s) + (warp >> 1) * 52 + min(8 * (warp & 1) + g, 12) * 4;
        uint32_t w2b = w2a + min(24 + t, 25) * 448 + (min(24 + t, 25) & 1) * 8, w2c = w2a + 25 * 448 + 8;
        w2a += t * 448 + (t & 1) * 8;
        asm volatile("" : "+r"(w2a), "+r"(w2b), "+r"(w2c));
        float m0 = 0.f, m1 = 0.f, m2 = 0.f, m3 = 0.f;
        float w3f[26];
#pragma unroll
        for (int q = 0; q < 26; q++) { w3f[q] = (q & 1) ? bf_hi(w3w[q >> 1]) : bf_lo(w3w[q >> 1]); asm volatile("" : "+f"(w3f[q])); }
#define MROW(q, ma, mb) { const uint32_t v = W3s[(q) * 338 + p]; ma = fmaf(w3f[q], bf_lo(v), ma); mb = fmaf(w3f[q], bf_hi(v), mb); }
        mbar_wait(bar + 8);
        MROW(0, m0, m1) MROW(1, m2, m3) MROW(2, m0, m1) MROW(3, m2, m3) MROW(4, m0, m1) MROW(5, m2, m3) MROW(6, m0, m1)
        MROW(7, m2, m3) MROW(8, m0, m1) MROW(9, m2, m3) MROW(10, m0, m1) MROW(11, m2, m3) MROW(12, m0, m1) MROW(13, m2, m3)
        MROW(14, m0, m1) MROW(15, m2, m3) MROW(16, m0, m1) MROW(17, m2, m3) MROW(18, m0, m1) MROW(19, m2, m3)
        MROW(20, m0, m1) MROW(21, m2, m3) MROW(22, m0, m1) MROW(23, m2, m3) MROW(24, m0, m1) MROW(25, m2, m3)
#undef MROW
        if (tid < 338) {
            const int h = tid / 13, k = 2 * (tid - h * 13);
            uint32_t t0, t1;
            asm("cvt.rna.tf32.f32 %0, %1;" : "=r"(t0) : "f"(m0 + m2));
            asm("cvt.rna.tf32.f32 %0, %1;" : "=r"(t1) : "f"(m1 + m3));
            float* m = Ms + (h >> 2) * 128 + (k >> 3) * 32 + (k & 7) * 4 + (h & 3);
            m[0] = __uint_as_float(t0); m[4] = __uint_as_float(t1);
            if (tid < 26) Ms[(tid >> 2) * 128 + 3 * 32 + 2 * 4 + (tid & 3)] = __uint_as_float((uint32_t)wc2r << 16);
        }
        fence_async_smem();
        if (warp >= 8) asm volatile("bar.arrive 1, 352;" ::: "memory");
        if (warp < 8) {
            mbar_wait(bar + 32);
#pragma unroll
            for (int rd = 0; rd < 2; rd++)
#pragma unroll
                for (int ks = 0; ks < 4; ks++) {
                    const uint32_t p0 = lds32((ks < 3 ? w2a + ks * 3584 : w2b) + rd * 208);
                    const uint32_t p1 = lds32((ks < 3 ? w2a + ks * 3584 + 1792 : w2c) + rd * 208);
                    pa[rd][ks][0] = p0 << 16; pa[rd][ks][1] = p0 & 0xffff0000u; pa[rd][ks][2] = p1 << 16; pa[rd][ks][3] = p1 & 0xffff0000u;
                }
#pragma unroll
            for (int rd = 0; rd < 2; rd++)
#pragma unroll
                for (int ks = 0; ks < 4; ks++) asm volatile("" : "+r"(pa[rd][ks][0]), "+r"(pa[rd][ks][1]), "+r"(pa[rd][ks][2]), "+r"(pa[rd][ks][3]));
        }
    }
    uint32_t e1[8], e2[8];
    if (warp < 8) {
        asm volatile("bar.sync 1, 352;" ::: "memory");
        float c[2][16];
#pragma unroll
        for (int i = 0; i < 16; i++) { c[0][i] = 0.f; c[1][i] = 0.f; }
        const uint64_t db = mkdesc(smem_u32(Ms), 512, 128, 0);
        wg_fence();
#pragma unroll
        for (int rd = 0; rd < 2; rd++)
#pragma unroll
            for (int ks = 0; ks < 4; ks++)
                wgmma_tf32_n32(c[rd], pa[rd][ks][0], pa[rd][ks][1], pa[rd][ks][2], pa[rd][ks][3], db + ks * (1024 >> 4), ks != 0);
        wg_commit();
        wg_wait<0>();
#pragma unroll
        for (int i = 0; i < 16; i++) asm volatile("" : "+f"(c[0][i]), "+f"(c[1][i]) :: "memory");
        const int j = 16 * (warp & 1) + 2 * g;
        if (j < 26) {
#pragma unroll
            for (int rd = 0; rd < 2; rd++) {
                float* A = As + (4 * rd + (warp >> 1)) * FS;
#pragma unroll
                for (int nt = 0; nt < 4; nt++) {
                    *(float2*)(A + j * P + 8 * nt + 2 * t) = make_float2(c[rd][4 * nt], c[rd][4 * nt + 1]);
                    *(float2*)(A + (j + 1) * P + 8 * nt + 2 * t) = make_float2(c[rd][4 * nt + 2], c[rd][4 * nt + 3]);
                }
            }
        }
    } else {
        mbar_wait(bar + 40);
        const uint16_t* W = W1s + min(r, min(25 - 8 * f, 7)) * 676;
#pragma unroll 1
        for (int it = warp >= 11 ? warp - 11 : warp + 2; it < (warp >= 11 ? 10 : 12); it += 5) {
            const int oc = it * 4 + (lane >> 3);
            const uint4 ta = tabs[96 + 2 * oc], tb = tabs[96 + 2 * oc + 1];
            const uint32_t tv[8] = {ta.x, ta.y, ta.z, ta.w, tb.x, tb.y, tb.z, tb.w};
            uint32_t x[8], y[8];
#pragma unroll
            for (int e = 0; e < 8; e++) { x[e] = W[min(tv[e] & 0xffffu, 675u)]; y[e] = W[min(tv[e] >> 16, 675u)]; }
            float s1[8];
#pragma unroll
            for (int e = 0; e < 8; e++)
                s1[e] = ((tv[e] & 0xffffu) < 676u ? __uint_as_float(x[e] << 16) : 0.f) + ((tv[e] >> 16) < 676u ? __uint_as_float(y[e] << 16) : 0.f);
            const uint4 o = make_uint4(pack_bf16(s1[0], s1[1]), pack_bf16(s1[2], s1[3]), pack_bf16(s1[4], s1[5]), pack_bf16(s1[6], s1[7]));
            *(uint4*)(img + (oc / 12) * 3072 + (r >> 2) * 1536 + (oc % 12) * 128 + (r & 3) * 32) = live ? o : make_uint4(0, 0, 0, 0);
        }
    }
    if (warp < 12) {
        mbar_wait(bar + 40);
        const uint4 tab0 = tabs[2 * oct], tab1 = tabs[2 * oct + 1];
        const uint32_t tw[8] = {tab0.x, tab0.y, tab0.z, tab0.w, tab1.x, tab1.y, tab1.z, tab1.w};
        const uint32_t A = smem_u32(As + r * FS);
#pragma unroll
        for (int e = 0; e < 8; e++) { e1[e] = A + (tw[e] & 0xffffu); e2[e] = A + (tw[e] >> 16); asm volatile("" : "+r"(e1[e]), "+r"(e2[e])); }
    }
    __syncthreads();
    if (warp < 12) {
        float s2[8];
#pragma unroll
        for (int e = 0; e < 8; e++) s2[e] = lds32f(e1[e]) + lds32f(e2[e]);
        const uint4 o = make_uint4(pack_bf16(s2[0], s2[1]), pack_bf16(s2[2], s2[3]), pack_bf16(s2[4], s2[5]), pack_bf16(s2[6], s2[7]));
        *(uint4*)(out16 + 16) = live ? o : make_uint4(0, 0, 0, 0);
    }
    fence_async_smem();
    __syncthreads();
    if (warp == 0) {
        if (lane < 4) {
            asm volatile("cp.async.bulk.global.shared::cta.bulk_group [%0], [%1], %2;"
                         :: "l"(cinw + lane * CW_BLK + f * 3072), "r"(smem_u32(img) + lane * 3072), "r"(f < 3 ? 3072 : 1536) : "memory");
            asm volatile("cp.async.bulk.commit_group;" ::: "memory");
            asm volatile("cp.async.bulk.wait_group 0;" ::: "memory");
        }
        __syncwarp();
        if (lane < kFlags) asm volatile("red.relaxed.gpu.global.add.u32 [%0], 1;" :: "l"(sync + lane * 32) : "memory");
    }
}

__global__ void __cluster_dims__(2, 1, 1) __launch_bounds__(kThreads, 1)
xdeepfm_kernel(const int* __restrict__ idx, const uint8_t* __restrict__ table, const __nv_bfloat16* __restrict__ ws_cin,
               const uint4* __restrict__ tab, const uint8_t* __restrict__ w_dnn1, const __nv_bfloat16* __restrict__ w_cin_out,
               const __nv_bfloat16* __restrict__ b_dnn1, const __nv_bfloat16* __restrict__ w_dnn2, const __nv_bfloat16* __restrict__ b_out,
               __nv_bfloat16* __restrict__ out, uint8_t* __restrict__ cinw, unsigned int* sync,
               const __grid_constant__ CUtensorMap tm128, const __grid_constant__ CUtensorMap tm32) {
    extern __shared__ __align__(1024) uint8_t smem[];
    const uint32_t t_entry = clock();
    const int lane = threadIdx.x & 31;
    const int warp = __shfl_sync(0xffffffffu, threadIdx.x >> 5, 0);
    const int tid = threadIdx.x;
    const uint32_t sb = smem_u32(smem);
    if (blockIdx.x < kFold) {
        fold_issue(sb, tid, (const uint8_t*)ws_cin, tab);
        fold_role(smem, w_cin_out, cinw, sync);
        return;
    }
    const int cta = blockIdx.x - kFold;
    const uint32_t rank = blockIdx.x & 1;
    const int q = lane >> 2, c = lane & 3, w4 = warp & 3;

    const int gw = warp - 4;
    const int gh = lane & 1, gs = (lane >> 1) & 7, gf = (gw >> 2) * 2 + (lane >> 4);
    uint4 iv = make_uint4(0, 0, 0, 0);
    if (warp >= 4 && warp < 12) {
        const int t = min(tid - 128, 207);
        asm volatile("ld.global.nc.v4.b32 {%0,%1,%2,%3}, [%4];" : "=r"(iv.x), "=r"(iv.y), "=r"(iv.z), "=r"(iv.w) : "l"(idx + cta * 832 + t * 4));
    } else if (warp == 12) {
        if (lane == 0) {
#pragma unroll
            for (int i = 0; i < 7; i++) { mbar_init(sb + B_XLOC + i * 8, i < 6 ? 256 : 128 + 4); mbar_init(sb + B_DFULL + i * 8, 1); }
#pragma unroll
            for (int i = 0; i < 3; i++) mbar_init(sb + B_SLOT + i * 8, 1);
#pragma unroll
            for (int i = 0; i < 4; i++) mbar_init(sb + B_CINW + i * 8, 1);
            mbar_init(sb + B_CINREQ, 1);
            mbar_init(sb + B_FIN, 3);
            asm volatile("fence.mbarrier_init.release.cluster;" ::: "memory");
            fence_async_smem();
#pragma unroll
            for (int i = 0; i < 7; i++) mbar_expect_tx(sb + B_DFULL + i * 8, WSLOT + 2048 + (i < 6 ? 4 * XF : 2 * XF));
#pragma unroll
            for (int i = 0; i < 4; i++) mbar_expect_tx(sb + B_CINW + i * 8, CW_BLK);
            mbar_expect_tx(sb + B_FIN, 128);
        }
    } else if (warp == 13) {
        if (lane == 0) {
            if (cta < 127) asm volatile("cp.async.bulk.prefetch.L2.global [%0], %1;" :: "l"((const uint8_t*)ws_cin + cta * 832), "r"(cta < 126 ? 832 : 624) : "memory");
            asm volatile("prefetch.tensormap [%0];" :: "l"(&tm128) : "memory");
            asm volatile("prefetch.tensormap [%0];" :: "l"(&tm32) : "memory");
            asm volatile("cp.async.bulk.prefetch.L2.global [%0], %1;" :: "l"(w_dnn1 + cta * 2704), "r"(2704) : "memory");
        }
    }
    __syncthreads();
    asm volatile("barrier.cluster.arrive.relaxed.aligned;" ::: "memory");

    if (warp >= 12) {
        asm volatile("setmaxnreg.dec.sync.aligned.u32 24;");
        if (warp == 12) {
            if (lane == 0) {
#pragma unroll 1
                for (int ch = 0; ch < 7; ch++) {
                    if (ch == 0) { while ((uint32_t)clock() - t_entry < kW1Start) {} }
                    else { const uint32_t t0 = clock(); while ((uint32_t)clock() - t0 < kW1Gap) {} }
                    if (ch == kW1AfterCin) mbar_wait(sb + B_CINREQ);
                    if (ch >= 4) mbar_wait(sb + B_SLOT + (ch - 4) * 8);
                    tma3(sb + (ch & 3) * WSLOT, &tm128, 0, ch * 64, rank * 3, sb + B_DFULL + ch * 8);
                    tma3(sb + WS_OFF + ch * 2048, &tm32, 0, ch * 64, 24 + rank, sb + B_DFULL + ch * 8);
                }
            }
            __syncwarp();
            asm volatile("barrier.cluster.wait.aligned;" ::: "memory");
        } else if (warp == 13) {
            asm volatile("barrier.cluster.wait.aligned;" ::: "memory");
            if (lane == 0) {
                const uint32_t src = sb + X_OFF + rank * XB, rd = mapa(src, rank ^ 1), rb = mapa(sb + B_DFULL, rank ^ 1);
#pragma unroll 1
                for (int ch = 0; ch < 7; ch++) {
                    mbar_wait(sb + B_XLOC + ch * 8);
                    fence_async_smem();
                    asm volatile("cp.async.bulk.shared::cluster.shared::cta.mbarrier::complete_tx::bytes [%0], [%1], %2, [%3];"
                                 :: "r"(rd + ch * 4 * XF), "r"(src + ch * 4 * XF), "r"(ch < 6 ? 4 * XF : 2 * XF), "r"(rb + ch * 8) : "memory");
                }
            }
        } else if (warp == 14) {
            asm volatile("barrier.cluster.wait.aligned;" ::: "memory");
            if (lane == 0) {
                while ((uint32_t)clock() - t_entry < kPollStart) {}
                const unsigned int* flag = sync + (cta % kFlags) * 32;
                uint32_t v0 = 0, v1 = 0, it = 0;
                asm volatile("ld.relaxed.gpu.global.u32 %0, [%1];" : "=r"(v0) : "l"(flag) : "memory");
                { const uint32_t t0 = clock(); while ((uint32_t)clock() - t0 < 300u) {} }
                asm volatile("ld.relaxed.gpu.global.u32 %0, [%1];" : "=r"(v1) : "l"(flag) : "memory");
#pragma unroll 1
                for (; it < (1u << 22); it++) {
                    if (v0 >= (uint32_t)kFold) break;
                    asm volatile("ld.relaxed.gpu.global.u32 %0, [%1];" : "=r"(v0) : "l"(flag) : "memory");
                    if (v1 >= (uint32_t)kFold) break;
                    asm volatile("ld.relaxed.gpu.global.u32 %0, [%1];" : "=r"(v1) : "l"(flag) : "memory");
                }
                if (it == (1u << 22)) __trap();
                asm volatile("fence.proxy.async.global;" ::: "memory");
#pragma unroll
                for (int i = 0; i < 4; i++)
                    asm volatile("cp.async.bulk.shared::cluster.global.mbarrier::complete_tx::bytes [%0], [%1], %2, [%3];"
                                 :: "r"(sb + CW_OFF + i * CW_BLK), "l"(cinw + i * CW_BLK), "r"(CW_BLK), "r"(sb + B_CINW + i * 8) : "memory");
                mbar_arrive(sb + B_CINREQ);
                if (atomicAdd(sync + kFlags * 32, 1u) == kMain - 1) {
#pragma unroll 1
                    for (int i = 0; i <= kFlags; i++) sync[i * 32] = 0;
                }
            }
        } else {
            asm volatile("barrier.cluster.wait.aligned;" ::: "memory");
        }
    } else if (warp < 4) {
        asm volatile("setmaxnreg.inc.sync.aligned.u32 168;");
        {
            float2* bw = (float2*)(smem + BW_OFF);
            const int hid = rank * 192 + tid;
            bw[tid] = make_float2(bf2f(b_dnn1 + hid), 0.5f * bf2f(w_dnn2 + hid));
            if (tid < 64) bw[tid + 128] = make_float2(bf2f(b_dnn1 + hid + 128), 0.5f * bf2f(w_dnn2 + hid + 128));
            else if (tid < 80) bw[tid + 128] = make_float2(bf2f(b_dnn1 + 320 + rank * 16 + tid), 0.5f * bf2f(w_dnn2 + 320 + rank * 16 + tid));
            if (tid == 127) sts32f(sb + PART_OFF + 256, bf2f(b_out));
            if (tid < 64) {
                const uint32_t ca = sb + X_OFF + rank * XB + 26 * XF + (tid >> 5) * XH + (tid & 31) * 16;
                asm volatile("st.shared.v4.b32 [%0], {%1,%1,%1,%1};" :: "r"(ca), "r"(0x3f803f80u) : "memory");
            }
            __syncwarp();
            if (lane == 0) mbar_arrive(sb + B_XLOC + 6 * 8);
        }
        asm volatile("barrier.cluster.wait.aligned;" ::: "memory");
        float acc[96], acs[8];
        asm volatile("bar.sync 2, 128;" ::: "memory");
#pragma unroll
        for (int g = 0; g < 26; g++) {
            const float4 bw = lds128f(sb + BW_OFF + (8 * g + 2 * c) * 8);
            float* v = g < 24 ? &acc[4 * g] : &acs[4 * (g - 24)];
            v[0] = bw.x; v[1] = bw.z; v[2] = bw.x; v[3] = bw.z;
        }
        const uint64_t db = mkdesc(sb, 8192, 1024, 1);
        const uint64_t ds = mkdesc(sb + WS_OFF, 256, 256, 3);
        const uint32_t la = sb + X_OFF + (w4 >> 1) * XB + (lane >> 4) * XH + (((2 * w4) & 3) + ((lane >> 3) & 1)) * 128 + (lane & 7) * 16;
#pragma unroll
        for (int ch = 0; ch < 7; ch++) {
            mbar_wait(sb + B_XLOC + ch * 8);
            mbar_wait(sb + B_DFULL + ch * 8);
            uint32_t a[4][4];
#pragma unroll
            for (int k = 0; k < 4; k++)
                if (k < 2 || ch < 6)
                    asm volatile("ldmatrix.sync.aligned.m8n8.x4.shared.b16 {%0,%1,%2,%3}, [%4];"
                                 : "=r"(a[k][0]), "=r"(a[k][1]), "=r"(a[k][2]), "=r"(a[k][3]) : "r"(la + (4 * ch + k) * XF) : "memory");
            wg_fence();
#pragma unroll
            for (int k = 0; k < 4; k++)
                if (k < 2 || ch < 6) {
                    wgmma_rs_n192(acc, a[k], db + (((ch & 3) * WSLOT + k * 2048) >> 4), 1);
                    wgmma_rs_n16(acs, a[k], ds + ((ch * 2048 + k * 512) >> 4), 1);
                }
            wg_commit();
            if (ch < 3) {
                wg_wait<0>();
                if (tid == 0) mbar_arrive(sb + B_SLOT + ch * 8);
            } else {
                wg_wait<1>();
            }
        }
        wg_wait<0>();
#pragma unroll
        for (int i = 0; i < 96; i++) asm volatile("" : "+f"(acc[i]) :: "memory");
#pragma unroll
        for (int i = 0; i < 8; i++) asm volatile("" : "+f"(acs[i]) :: "memory");
        float s0 = 0.f, s1 = 0.f, s2 = 0.f, s3 = 0.f;
#pragma unroll
        for (int g = 0; g < 26; g++) {
            const float4 bw = lds128f(sb + BW_OFF + (8 * g + 2 * c) * 8);
            const float* v = g < 24 ? &acc[4 * g] : &acs[4 * (g - 24)];
            gelu_dot(v[0], bw.y, s0);
            gelu_dot(v[1], bw.w, s2);
            gelu_dot(v[2], bw.y, s1);
            gelu_dot(v[3], bw.w, s3);
        }
        s0 += s2; s1 += s3;
        s0 += __shfl_xor_sync(0xffffffffu, s0, 1); s1 += __shfl_xor_sync(0xffffffffu, s1, 1);
        s0 += __shfl_xor_sync(0xffffffffu, s0, 2); s1 += __shfl_xor_sync(0xffffffffu, s1, 2);
        const uint32_t r = (w4 & 1) * 16 + q;
        if ((uint32_t)(w4 >> 1) == rank) {
            if (c == 0) { sts32f(sb + PART_OFF + r * 4, s0); sts32f(sb + PART_OFF + (r + 8) * 4, s1); }
            __syncwarp();
            if (lane == 0) mbar_arrive(sb + B_FIN);
        } else if (c == 0) {
            const uint32_t ra = mapa(sb + PART_OFF + (32 + r) * 4, rank ^ 1), rb = mapa(sb + B_FIN, rank ^ 1);
            asm volatile("st.async.weak.shared::cluster.mbarrier::complete_tx::bytes.f32 [%0], %1, [%2];" :: "r"(ra), "f"(s0), "r"(rb) : "memory");
            asm volatile("st.async.weak.shared::cluster.mbarrier::complete_tx::bytes.f32 [%0], %1, [%2];" :: "r"(ra + 32), "f"(s1), "r"(rb) : "memory");
        }
    } else {
        asm volatile("setmaxnreg.inc.sync.aligned.u32 160;");
        const uint32_t dst = sb + X_OFF + rank * XB + gf * XF + gh * XH + (gw & 3) * 128 + gs * 16;
        uint32_t row[7];
        if (tid - 128 < 208) asm volatile("st.shared.v4.b32 [%0], {%1,%2,%3,%4};" :: "r"(sb + IDX_OFF + (tid - 128) * 16), "r"(iv.x), "r"(iv.y), "r"(iv.z), "r"(iv.w) : "memory");
        asm volatile("bar.sync 1, 256;" ::: "memory");
#pragma unroll
        for (int it = 0; it < 7; it++) row[it] = lds32(sb + IDX_OFF + (((gw & 3) * 8 + gs) * 26 + gf + ((it < 6 || gw < 4) ? it * 4 : 0)) * 4);
#pragma unroll
        for (int it = 0; it < 7; it++) {
            if (it < 6 || gw < 4) {
                asm volatile("cp.async.cg.shared.global [%0], [%1], 16;" :: "r"(dst + it * 4 * XF), "l"(table + (size_t)row[it] * 32 + gh * 16) : "memory");
                asm volatile("cp.async.mbarrier.arrive.noinc.shared::cta.b64 [%0];" :: "r"(sb + B_XLOC + it * 8) : "memory");
            }
            if (it < 6) { const uint32_t t0 = clock(); while ((uint32_t)clock() - t0 < kGatherPace) {} }
        }
        asm volatile("barrier.cluster.wait.aligned;" ::: "memory");
#pragma unroll 1
        for (int ch = 0; ch < 7; ch++) mbar_wait(sb + B_XLOC + ch * 8);
        const int wg = warp >> 2;
        const uint32_t xb = sb + X_OFF + rank * XB + (q >> 2) * XH + (q & 3) * 4 + ((wg - 1) * 16 + w4) * 16;
        XAddr xa;
        xa.LA = xb + (c == 1 ? 14 : 0) * XF; xa.LB = xb + (c == 1 ? 1 : 0) * XF;
        xa.RA = xb + (c == 0 ? 0 : c == 3 ? 21 : 14) * XF; xa.RB = xb + (c == 0 ? 0 : c == 3 ? 7 : 14) * XF;
        xa.RC = xb + (c == 0 ? 0 : c == 1 ? 1 : c == 2 ? 14 : 7) * XF;
        xa.RD = xb + (c == 0 ? -13 : c == 1 ? 1 : c == 2 ? 0 : 7) * (int)XF;
        xa.E = xb + (13 + 3 * c) * XF;
        const uint64_t db = mkdesc(sb + CW_OFF, 128, 1536, 0);
        const uint32_t pin = sb + CINP_OFF + (warp - 4) * 384 + lane * 4;
        XReg x0, x1, x2, x3;
        float dA[28], dB[28], s0, s1, s2, s3;
        cin_loads<0>(x0, xa, 0); cin_loads<1>(x0, xa, 0);
        mbar_wait(sb + B_CINW);
        cin_tile<false, true>(dA, dB, x0, x1, xa, 0, db, pin, sb + B_CINW);
        cin_tile<true, true>(dB, dA, x1, x2, xa, 64, db, pin, 0);
        cin_tile<true, true>(dA, dB, x2, x3, xa, 128, db, pin + 128, 0);
        cin_tile<true, false>(dB, dA, x3, x0, xa, 192, db, pin + 256, 0);
        s0 = lds32f(pin); s1 = lds32f(pin + 128); s2 = lds32f(pin + 256);
#pragma unroll
        for (int o = 16; o > 0; o >>= 1) {
            s0 += __shfl_xor_sync(0xffffffffu, s0, o);
            s1 += __shfl_xor_sync(0xffffffffu, s1, o);
            s2 += __shfl_xor_sync(0xffffffffu, s2, o);
        }
        const float w = lane < 8 ? s0 : lane < 16 ? s1 : s2;
        mbar_wait(sb + B_FIN);
        const int tl = lane >> 3;
        const int smp = (wg - 1) * 16 + 4 * tl + w4;
        const float base = lds32f(sb + PART_OFF + smp * 4) + lds32f(sb + PART_OFF + 128 + smp * 4) + lds32f(sb + PART_OFF + 256);
        wg_wait<0>();
        s3 = cin_dot(dB);
#pragma unroll
        for (int o = 16; o > 0; o >>= 1) s3 += __shfl_xor_sync(0xffffffffu, s3, o);
        if ((lane & 7) == 0) out[cta * 32 + smp] = __float2bfloat16((tl == 3 ? s3 : w) + base);
    }
}

typedef CUresult (*EncodeTiledFn)(CUtensorMap*, CUtensorMapDataType, cuuint32_t, void*, const cuuint64_t*, const cuuint64_t*,
                                  const cuuint32_t*, const cuuint32_t*, CUtensorMapInterleave, CUtensorMapSwizzle,
                                  CUtensorMapL2promotion, CUtensorMapFloatOOBfill);

void make_map(EncodeTiledFn enc, CUtensorMap* m, void* base, int inner, int box_atoms, CUtensorMapSwizzle sw) {
    cuuint64_t dims[3] = {(cuuint64_t)inner, 416, (cuuint64_t)(416 / inner)};
    cuuint64_t strides[2] = {832, (cuuint64_t)inner * 2};
    cuuint32_t box[3] = {(cuuint32_t)inner, 64, (cuuint32_t)box_atoms};
    cuuint32_t es[3] = {1, 1, 1};
    enc(m, CU_TENSOR_MAP_DATA_TYPE_BFLOAT16, 3, base, dims, strides, box, es, CU_TENSOR_MAP_INTERLEAVE_NONE, sw,
        CU_TENSOR_MAP_L2_PROMOTION_L2_128B, CU_TENSOR_MAP_FLOAT_OOB_FILL_NONE);
}

}

extern "C" void kernel_launch(void* const* d_in, const int* in_sizes, int n_in, void* d_out, int out_size) {
    (void)in_sizes; (void)n_in; (void)out_size;
    static EncodeTiledFn enc = nullptr;
    static void *p_tab, *p_cinw, *p_sync;
    if (!enc) {
        cudaGetSymbolAddress(&p_tab, g_tab);
        cudaGetSymbolAddress(&p_cinw, g_cinw);
        cudaGetSymbolAddress(&p_sync, g_sync);
        cudaFuncSetAttribute(xdeepfm_kernel, cudaFuncAttributeMaxDynamicSharedMemorySize, SMEM_BYTES);
        void* fn = nullptr;
        cudaDriverEntryPointQueryResult qr;
        cudaGetDriverEntryPoint("cuTensorMapEncodeTiled", &fn, cudaEnableDefault, &qr);
        enc = (EncodeTiledFn)fn;
    }
    CUtensorMap tm128, tm32;
    make_map(enc, &tm128, d_in[4], 64, 3, CU_TENSOR_MAP_SWIZZLE_128B);
    make_map(enc, &tm32, d_in[4], 16, 1, CU_TENSOR_MAP_SWIZZLE_32B);
    xdeepfm_kernel<<<kFold + kMain, kThreads, SMEM_BYTES, cudaStreamPerThread>>>(
        (const int*)d_in[0], (const uint8_t*)d_in[1], (const __nv_bfloat16*)d_in[2], (const uint4*)p_tab, (const uint8_t*)d_in[4],
        (const __nv_bfloat16*)d_in[3], (const __nv_bfloat16*)d_in[5], (const __nv_bfloat16*)d_in[6], (const __nv_bfloat16*)d_in[7],
        (__nv_bfloat16*)d_out, (uint8_t*)p_cinw, (unsigned int*)p_sync, tm128, tm32);
}
```
